```python
import torch

def _softmax(x, axis=-1):
    return torch.softmax(x, dim=axis)
def _gelu(x):
    return torch.nn.functional.gelu(x, approximate="tanh")
def _silu(x):
    return torch.nn.functional.silu(x)
def _sigmoid(x):
    return torch.sigmoid(x)
def _layernorm(x, axis=-1, eps=1e-5):
    m = x.mean(dim=axis, keepdim=True)
    v = x.var(dim=axis, keepdim=True, unbiased=False)
    return (x - m) / torch.sqrt(v + eps)
def _scatter_add(tgt, idx, src, axis=0):
    return tgt.clone().index_add_(axis, idx, src)
def _segment_sum(src, seg, n):
    out = torch.zeros((n,) + src.shape[1:], dtype=src.dtype)
    return out.index_add_(0, seg, src)
def _pad(x, pw):
    flat = tuple(v for pair in reversed(pw) for v in pair)
    return torch.nn.functional.pad(x, flat)

kernel_name = 'standalone__sliding_block_cached__sampling'

def setup_inputs():

    _w = (lambda a: (lambda t: t.to(torch.bfloat16) if t.is_floating_point() else t)(torch.as_tensor(a)))
    B, Sq, D = 8, 32, 448
    Hq, Hkv, Sk, Dh = 16, 8, 8192, 256
    assert Hq % Hkv == 0, (Hq, Hkv)
    return {
        "x": _w((lambda *s: torch.randn(*s, dtype=torch.bfloat16) * 0.8)(B, Sq, D)),
        "k_cache": _w((lambda *s: torch.randn(*s, dtype=torch.bfloat16) * 0.8)(B, Hkv, Sk, Dh)),
        "v_cache": _w((lambda *s: torch.randn(*s, dtype=torch.bfloat16) * 0.05)(B, Hkv, Sk, Dh)),
        "wq": _w((lambda *s: torch.randn(*s, dtype=torch.bfloat16) * 0.8)(D, Hq * Dh) * (D ** -0.5)),
        "wo": _w((lambda *s: torch.randn(*s, dtype=torch.bfloat16) * 0.05)(Hq * Dh, D) * ((Hq * Dh) ** -0.5)),
    }

def reference(x, k_cache, v_cache, wq, wo):
    B, Sq, D = x.shape
    Hq, Dh = 16, 256
    Hkv, Sk = k_cache.shape[1], k_cache.shape[2]
    W = min(4096, max(256, Sk // 4))
    rep = Hq // Hkv
    q = (lambda x, *d: x.permute(*d))((x @ wq).reshape(B, Sq, Hq, Dh), 0, 2, 1, 3)
    k = (lambda x, n, axis: torch.repeat_interleave(x, n, dim=axis))(k_cache[:, :, Sk - W:, :], rep, axis=1)
    v = (lambda x, n, axis: torch.repeat_interleave(x, n, dim=axis))(v_cache[:, :, Sk - W:, :], rep, axis=1)
    scores = torch.einsum("bhqd,bhkd->bhqk", q, k) * (Dh ** -0.5)
    p = _softmax(scores, axis=-1)
    o = torch.einsum("bhqk,bhkd->bhqd", p, v)
    return (lambda x, *d: x.permute(*d))(o, 0, 2, 1, 3).reshape(B, Sq, Hq * Dh) @ wo
```

```cpp
#include <cuda_runtime.h>
#include <cuda_bf16.h>
#include <cuda.h>
#include <stdint.h>

namespace {

constexpr int SQ = 32, DM = 448, SK = 8192, WIN = 2048;
constexpr int NT = 32;
constexpr int U = 16384;
constexpr int OFF_WQ = 3 * U, OFF_X = 10 * U, OFF_W = 10 * U, OFF_PO = 9 * U;
constexpr int OFF_BAR = 14 * U;
constexpr int OFF_EP = OFF_BAR + 248;
constexpr int OFF_TAB = OFF_BAR + 512;
constexpr int SMEM_BYTES = OFF_BAR + 512 + 640;

constexpr int KF = 0, VF = 3, PA = 6, KE = 7, VE = 10, PB = 13, WF = 14, SF = 21, SFREE = 28, QRDY = 29;
constexpr int RK = 3, RV = 3;

struct __align__(16) Sched {
    unsigned int kc[32], vc[32];
    unsigned int it[80];
    int n1, n2, n3, n;
    int wun[4];
    int oun;
};
constexpr Sched make_sched() {
    Sched s{};
    const int kun[3] = {0, 3, 5}, vun[3] = {2, 7, 8};
    const int wp[6] = {3, 5, 9, 13, 18, 26};
    int n = 0, seq = 2;
    auto item = [&](int unit, int fb, int type, int tile, int wb, int use) {
        s.it[n++] = unit | fb << 4 | type << 9 | tile << 12 | (use > 0 ? (wb << 17 | ((use - 1) & 1) << 22 | 1 << 23) : 0) | (unsigned)seq << 24;
        if (type < 2 || type == 5) seq++;
    };
    auto addk = [&](int t) { item(kun[t % RK], KF + t % RK, 0, t, KE + t % RK, t / RK); };
    auto addv = [&](int t) {
        if (t == 31) item(kun[31 % RK] + 1, SF, 5, t, QRDY, 2);
        else item(vun[t % RV], VF + t % RV, t < 28 ? 1 : 5, t, VE + t % RV, t / RV);
    };
    const int late0 = RK == 3 ? 29 : -1, late1 = 30;
    for (int t = 0; t < 32; t++) {
        const bool kr = t + RK < 32 || t == late0 || t == late1, vr = t + RV < 32;
        s.kc[t] = kun[t % RK] | (KF + t % RK) << 8 | ((t / RK) & 1) << 13 | (KE + t % RK) << 14 | (kr ? 1 : 0) << 19;
        s.vc[t] = vun[t % RV] | (VF + t % RV) << 8 | ((t / RV) & 1) << 13 | (VE + t % RV) << 14 | (vr ? 1 : 0) << 19;
    }
    s.vc[31] = (kun[31 % RK] + 1) | SF << 8 | 1 << 13;
    for (int t = 1; t < 4; t++) {
        if (t < RK) addk(t);
        if (t < RV) addv(t);
    }
    s.n1 = n;
    for (int t = -1; t < 32; t++) {
        const int r = t + 1;
        if (r < 32) {
            if (r + RK < 32) addk(r + RK);
            if (r + RK == 31) { if (1) addv(28); if (!1) addv(29); }
            if (r == late0) { item(kun[r % RK], WF + 2, 2, 2, KE + r % RK, r / RK + 1); s.wun[2] = kun[r % RK]; addv(30 - 1); }
            if (r == late1) { item(kun[r % RK], WF + 3, 2, 3, KE + r % RK, r / RK + 1); s.wun[3] = kun[r % RK]; if (1) addv(30); addv(31); }
            if (r == wp[0]) item(10, WF + 4, 2, 4, 0, 0);
            if (r == wp[1]) item(12, WF + 5, 2, 5, 0, 0);
            if (r == wp[2]) { s.n2 = n; item(10, WF + 6, 2, 6, 0, 0); }
            if (r == wp[2] + 1) { item(12, WF + 1, 2, 1, 0, 0); s.wun[1] = 12; }
            if (r == wp[3]) { s.n3 = n; item(10, WF + 0, 2, 0, 0, 0); s.wun[0] = 10; }
            if (r == wp[4] && 3 < 0) item(0, 0, 4, 2, 0, 0);
            if (r == wp[4] + 1 && 3 < 0) item(0, 0, 4, 3, 0, 0);
            if (r == wp[5]) item(0, 0, 3, 0, 0, 0);
        }
        if (t >= 0 && t + RV < 29 && !(1 && t + RV == 28)) addv(t + RV);
    }
    s.n = n;
    s.oun = RV == 2 ? 8 : kun[31 % RK];
    return s;
}
__device__ constexpr Sched SC = make_sched();
constexpr int OUN = SC.oun;
__device__ const Sched g_sched = SC;

constexpr int PW = 128;
__device__ __align__(1024) uint4 g_q[64 * 16 * 128];
__device__ __align__(1024) uint64_t g_part[8 * 16 * 16 * PW];
__device__ __align__(1024) unsigned int g_qcnt[64 * 4 * 32];
__device__ __align__(1024) unsigned int g_pcnt[8 * 28 * 32];
__device__ unsigned int g_epoch[128 * 8];
#define STAMP(i) do {} while (0)
#define STAMP2(i) do {} while (0)
#define CK_(i) do {} while (0)
#define GT_(i) do {} while (0)
#define CKF_(i, ev) do {} while (0)
#define TIC() do {} while (0)
#define TOC(acc) do {} while (0)

#define CK1_(i) do {} while (0)
#define TIMEOUT(code) __trap();
__device__ __forceinline__ uint32_t smem_u32(const void* p) { return (uint32_t)__cvta_generic_to_shared(p); }
__device__ __forceinline__ void mbar_init(uint32_t bar, uint32_t cnt) {
    asm volatile("mbarrier.init.shared::cta.b64 [%0], %1;" :: "r"(bar), "r"(cnt) : "memory");
}
__device__ __forceinline__ void mbar_expect_tx(uint32_t bar, uint32_t bytes) {
    asm volatile("mbarrier.arrive.expect_tx.shared::cta.b64 _, [%0], %1;" :: "r"(bar), "r"(bytes) : "memory");
}
__device__ __forceinline__ void mbar_arrive(uint32_t bar) {
    asm volatile("mbarrier.arrive.shared::cta.b64 _, [%0];" :: "r"(bar) : "memory");
}
__device__ __forceinline__ void mbar_arrive_remote(uint32_t bar_cluster) {
    asm volatile("mbarrier.arrive.shared::cluster.b64 _, [%0];" :: "r"(bar_cluster) : "memory");
}
__device__ __forceinline__ void mbar_arrive2_pred(uint32_t bar, uint32_t rbar, uint32_t pred) {
    asm volatile("{\n.reg .pred p;\nsetp.ne.u32 p, %2, 0;\n@p mbarrier.arrive.shared::cta.b64 _, [%0];\n@p mbarrier.arrive.shared::cluster.b64 _, [%1];\n}" :: "r"(bar), "r"(rbar), "r"(pred) : "memory");
}
__device__ __forceinline__ void mbar_arrive_pred(uint32_t bar, uint32_t pred) {
    asm volatile("{\n.reg .pred p;\nsetp.ne.u32 p, %1, 0;\n@p mbarrier.arrive.shared::cta.b64 _, [%0];\n}" :: "r"(bar), "r"(pred) : "memory");
}
__device__ __forceinline__ bool mbar_try(uint32_t bar, uint32_t parity) {
    uint32_t ok;
    asm volatile("{\n.reg .pred p;\nmbarrier.try_wait.parity.shared::cta.b64 p, [%1], %2;\nselp.u32 %0, 1, 0, p;\n}"
                 : "=r"(ok) : "r"(bar), "r"(parity) : "memory");
    return ok != 0;
}
__device__ __forceinline__ bool mbar_test(uint32_t bar, uint32_t parity) {
    uint32_t ok;
    asm volatile("{\n.reg .pred p;\nmbarrier.test_wait.parity.shared::cta.b64 p, [%1], %2;\nselp.u32 %0, 1, 0, p;\n}"
                 : "=r"(ok) : "r"(bar), "r"(parity) : "memory");
    return ok != 0;
}
__device__ __forceinline__ void mbar_wait(uint32_t bar, uint32_t parity) {
    uint32_t n = 0;
    while (!mbar_try(bar, parity)) { if (++n > (1u << 20)) TIMEOUT((bar >> 3) & 31) }
}
__device__ __forceinline__ void mbar_wait_cluster(uint32_t bar, uint32_t parity) {
    for (uint32_t n = 0;; n++) {
        uint32_t ok;
        asm volatile("{\n.reg .pred p;\nmbarrier.try_wait.parity.acquire.cluster.shared::cta.b64 p, [%1], %2;\nselp.u32 %0, 1, 0, p;\n}"
                     : "=r"(ok) : "r"(bar), "r"(parity) : "memory");
        if (ok) break;
        if (n > (1u << 20)) TIMEOUT(44)
    }
}
#define PBWAIT() mbar_wait(bars + 8 * PB, 0)
__device__ __forceinline__ uint32_t mapa(uint32_t addr, uint32_t rank) {
    uint32_t r; asm("mapa.shared::cluster.u32 %0, %1, %2;" : "=r"(r) : "r"(addr), "r"(rank)); return r;
}
constexpr uint64_t EVF = 0x12F0000000000000ull;
__device__ __forceinline__ void tma_v(uint32_t dst, const CUtensorMap* m, uint32_t bar, int key, int c1, int c0) {
    asm volatile("cp.async.bulk.tensor.4d.shared::cluster.global.mbarrier::complete_tx::bytes.L2::cache_hint [%0], [%1, {%3, %4, %5, %6}], [%2], %7;"
        :: "r"(dst), "l"(m), "r"(bar), "r"(0), "r"(key), "r"(c1), "r"(c0), "l"(EVF) : "memory");
}
__device__ __forceinline__ void tma4d_mc(uint32_t dst, const CUtensorMap* m, uint32_t bar, int c3) {
    asm volatile("cp.async.bulk.tensor.4d.shared::cluster.global.mbarrier::complete_tx::bytes.multicast::cluster.L2::cache_hint [%0], [%1, {%3, %3, %3, %4}], [%2], %5, %6;"
        :: "r"(dst), "l"(m), "r"(bar), "r"(0), "r"(c3), "h"((uint16_t)3), "l"(EVF) : "memory");
}
__device__ __forceinline__ void tma_wo(uint32_t dst, const CUtensorMap* m, uint32_t bar, int col, int c0, int g4) {
    asm volatile("cp.async.bulk.tensor.4d.shared::cluster.global.mbarrier::complete_tx::bytes [%0], [%1, {%3, %4, %5, %6}], [%2];"
        :: "r"(dst), "l"(m), "r"(bar), "r"(col), "r"(0), "r"(c0), "r"(g4) : "memory");
}
__device__ __forceinline__ void dsmem_copy(uint32_t dst_cluster, uint32_t src, uint32_t bytes, uint32_t bar_cluster) {
    asm volatile("cp.async.bulk.shared::cluster.shared::cta.mbarrier::complete_tx::bytes [%0], [%1], %2, [%3];"
        :: "r"(dst_cluster), "r"(src), "r"(bytes), "r"(bar_cluster) : "memory");
}
__device__ __forceinline__ void tma2d(uint32_t dst, const CUtensorMap* m, uint32_t bar, int c0, int c1) {
    asm volatile("cp.async.bulk.tensor.2d.shared::cluster.global.mbarrier::complete_tx::bytes [%0], [%1, {%3, %4}], [%2];"
        :: "r"(dst), "l"(m), "r"(bar), "r"(c0), "r"(c1) : "memory");
}
__device__ __forceinline__ void tma2d_mc(uint32_t dst, const CUtensorMap* m, uint32_t bar, int c0, int c1) {
    asm volatile("cp.async.bulk.tensor.2d.shared::cluster.global.mbarrier::complete_tx::bytes.multicast::cluster [%0], [%1, {%3, %4}], [%2], %5;"
        :: "r"(dst), "l"(m), "r"(bar), "r"(c0), "r"(c1), "h"((uint16_t)3) : "memory");
}
__device__ __forceinline__ void fence_async() { asm volatile("fence.proxy.async.shared::cta;" ::: "memory"); }
__device__ __forceinline__ void wg_fence() { asm volatile("wgmma.fence.sync.aligned;" ::: "memory"); }
__device__ __forceinline__ void wg_commit() { asm volatile("wgmma.commit_group.sync.aligned;" ::: "memory"); }
template <int N> __device__ __forceinline__ void wg_wait() { asm volatile("wgmma.wait_group.sync.aligned %0;" :: "n"(N) : "memory"); }
__device__ __forceinline__ bool bar_any(int id, int n, bool v) {
    uint32_t r;
    asm volatile("{\n.reg .pred p, q;\nsetp.ne.u32 p, %3, 0;\nbar.red.or.pred q, %1, %2, p;\nselp.u32 %0, 1, 0, q;\n}" : "=r"(r) : "r"(id), "r"(n), "r"((uint32_t)v) : "memory");
    return r != 0;
}
__device__ __forceinline__ void bar_sync(int id, int n) { asm volatile("bar.sync %0, %1;" :: "r"(id), "r"(n) : "memory"); }
__device__ __forceinline__ float ex2(float x) { float y; asm("ex2.approx.ftz.f32 %0, %1;" : "=f"(y) : "f"(x)); return y; }
__device__ __forceinline__ uint32_t pack_bf16(float lo, float hi) {
    uint32_t r; asm("cvt.rn.bf16x2.f32 %0, %1, %2;" : "=r"(r) : "f"(hi), "f"(lo)); return r;
}
__device__ __forceinline__ uint4 ld_relaxed(const uint4* p) {
    uint4 v;
    asm volatile("ld.relaxed.gpu.global.v4.u32 {%0, %1, %2, %3}, [%4];" : "=r"(v.x), "=r"(v.y), "=r"(v.z), "=r"(v.w) : "l"(p) : "memory");
    return v;
}
__device__ __forceinline__ void st_relaxed(uint4* p, uint32_t a, uint32_t b, uint32_t c, uint32_t d) {
    asm volatile("st.relaxed.gpu.global.v4.u32 [%0], {%1, %2, %3, %4};" :: "l"(p), "r"(a), "r"(b), "r"(c), "r"(d) : "memory");
}
__device__ __forceinline__ bool valid(const uint4& v) { return v.x && v.y && v.z && v.w; }
__device__ __forceinline__ uint32_t ld_relaxed32(const unsigned int* p) {
    uint32_t v; asm volatile("ld.relaxed.gpu.global.u32 %0, [%1];" : "=r"(v) : "l"(p) : "memory"); return v;
}
__device__ __forceinline__ void cnt_inc(unsigned int* p, uint32_t pred) {
    asm volatile("{\n.reg .pred p;\nsetp.ne.u32 p, %1, 0;\n@p red.relaxed.gpu.global.add.u32 [%0], 1;\n}" :: "l"(p), "r"(pred) : "memory");
}
__device__ __forceinline__ void cnt_wait(unsigned int* p, uint32_t target, int lane) {
    uint32_t n = 0;
    for (;;) {
        uint32_t x = 0;
        asm volatile("{\n.reg .pred p;\nsetp.eq.u32 p, %2, 0;\n@p atom.relaxed.gpu.global.add.u32 %0, [%1], 0;\n}" : "+r"(x) : "l"(p), "r"(lane) : "memory");
        if ((int)(__shfl_sync(0xffffffffu, x, 0) - target) >= 0) break;
        if (++n > (1u << 20)) TIMEOUT(40)
        __nanosleep(50);
    }
}
__device__ __forceinline__ void cnt_wait_fast(unsigned int* p, uint32_t target, int lane) {
    constexpr int NP = 1;
    uint32_t x[NP];
#pragma unroll
    for (int i = 0; i < NP; i++) {
        x[i] = 0;
        asm volatile("{\n.reg .pred p;\nsetp.eq.u32 p, %2, 0;\n@p atom.relaxed.gpu.global.add.u32 %0, [%1], 0;\n}" : "+r"(x[i]) : "l"(p), "r"(lane) : "memory");
        if (i + 1 < NP) __nanosleep(100);
    }
    for (uint32_t n = 0;; n++) {
        bool done = false;
#pragma unroll
        for (int i = 0; i < NP; i++) {
            if (__shfl_sync(0xffffffffu, x[i], 0) == target) { done = true; break; }
            asm volatile("{\n.reg .pred p;\nsetp.eq.u32 p, %2, 0;\n@p atom.relaxed.gpu.global.add.u32 %0, [%1], 0;\n}" : "+r"(x[i]) : "l"(p), "r"(lane) : "memory");
        }
        if (done) break;
        if (n > (1u << 20)) TIMEOUT(41)
    }
}
__device__ __forceinline__ uint32_t lds32(uint32_t a) {
    uint32_t v; asm volatile("ld.shared.u32 %0, [%1];" : "=r"(v) : "r"(a) : "memory"); return v;
}
__device__ __forceinline__ int fresh_tid() { int v; asm volatile("mov.u32 %0, %%tid.x;" : "=r"(v)); return v; }
__device__ __forceinline__ int fresh_cta() { int v; asm volatile("mov.u32 %0, %%ctaid.x;" : "=r"(v)); return v; }
__device__ __forceinline__ void prefetch_l2(const void* p) { asm volatile("prefetch.global.L2 [%0];" :: "l"(p) : "memory"); }
__device__ __forceinline__ void touch_l2(const void* p) {
    uint32_t d; asm volatile("ld.global.nc.L1::no_allocate.L2::128B.u32 %0, [%1];" : "=r"(d) : "l"(p) : "memory");
}
__device__ __forceinline__ uint64_t make_desc(uint32_t addr, uint32_t lbo, uint32_t sbo) {
    return (uint64_t)((addr & 0x3FFFF) >> 4) | ((uint64_t)(lbo >> 4) << 16) | ((uint64_t)(sbo >> 4) << 32) | (1ull << 62);
}
template <int N> __device__ __forceinline__ void reg_fence(uint32_t (&d)[N]) {
#pragma unroll
    for (int i = 0; i < N; i++) asm volatile("" : "+r"(d[i]) :: "memory");
}
template <int N> __device__ __forceinline__ void reg_fence(uint32_t (&d)[N][4]) {
#pragma unroll
    for (int i = 0; i < N; i++) reg_fence(d[i]);
}
template <int N> __device__ __forceinline__ void reg_fence(float (&d)[N]) {
#pragma unroll
    for (int i = 0; i < N; i++) asm volatile("" : "+f"(d[i]) :: "memory");
}

__device__ __forceinline__ void wgmma_ss_n64_tb(float (&d)[32], uint64_t da, uint64_t db, int scale_d) {
    asm volatile("{\n.reg .pred p;\nsetp.ne.b32 p, %34, 0;\n"
        "wgmma.mma_async.sync.aligned.m64n64k16.f32.bf16.bf16 "
        "{%0, %1, %2, %3, %4, %5, %6, %7, %8, %9, %10, %11, %12, %13, %14, %15, %16, %17, %18, %19, %20, %21, %22, %23, %24, %25, %26, %27, %28, %29, %30, %31}, "
        "%32, %33, p, 1, 1, 0, 1;\n}\n"
        : "+f"(d[0]), "+f"(d[1]), "+f"(d[2]), "+f"(d[3]), "+f"(d[4]), "+f"(d[5]), "+f"(d[6]), "+f"(d[7]), "+f"(d[8]), "+f"(d[9]), "+f"(d[10]), "+f"(d[11]), "+f"(d[12]), "+f"(d[13]), "+f"(d[14]), "+f"(d[15]), "+f"(d[16]), "+f"(d[17]), "+f"(d[18]), "+f"(d[19]), "+f"(d[20]), "+f"(d[21]), "+f"(d[22]), "+f"(d[23]), "+f"(d[24]), "+f"(d[25]), "+f"(d[26]), "+f"(d[27]), "+f"(d[28]), "+f"(d[29]), "+f"(d[30]), "+f"(d[31])
        : "l"(da), "l"(db), "r"(scale_d));
}

__device__ __forceinline__ void wgmma_rs_n64(float (&d)[32], uint32_t a0, uint32_t a1, uint32_t a2, uint32_t a3, uint64_t db, int scale_d) {
    asm volatile("{\n.reg .pred p;\nsetp.ne.b32 p, %37, 0;\n"
        "wgmma.mma_async.sync.aligned.m64n64k16.f32.bf16.bf16 "
        "{%0, %1, %2, %3, %4, %5, %6, %7, %8, %9, %10, %11, %12, %13, %14, %15, %16, %17, %18, %19, %20, %21, %22, %23, %24, %25, %26, %27, %28, %29, %30, %31}, "
        "{%32, %33, %34, %35}, %36, p, 1, 1, 0;\n}\n"
        : "+f"(d[0]), "+f"(d[1]), "+f"(d[2]), "+f"(d[3]), "+f"(d[4]), "+f"(d[5]), "+f"(d[6]), "+f"(d[7]), "+f"(d[8]), "+f"(d[9]), "+f"(d[10]), "+f"(d[11]), "+f"(d[12]), "+f"(d[13]), "+f"(d[14]), "+f"(d[15]), "+f"(d[16]), "+f"(d[17]), "+f"(d[18]), "+f"(d[19]), "+f"(d[20]), "+f"(d[21]), "+f"(d[22]), "+f"(d[23]), "+f"(d[24]), "+f"(d[25]), "+f"(d[26]), "+f"(d[27]), "+f"(d[28]), "+f"(d[29]), "+f"(d[30]), "+f"(d[31])
        : "r"(a0), "r"(a1), "r"(a2), "r"(a3), "l"(db), "r"(scale_d));
}

__device__ __forceinline__ void wgmma_rs_n128_tb(float (&d)[64], uint32_t a0, uint32_t a1, uint32_t a2, uint32_t a3, uint64_t db, int scale_d) {
    asm volatile("{\n.reg .pred p;\nsetp.ne.b32 p, %69, 0;\n"
        "wgmma.mma_async.sync.aligned.m64n128k16.f32.bf16.bf16 "
        "{%0, %1, %2, %3, %4, %5, %6, %7, %8, %9, %10, %11, %12, %13, %14, %15, %16, %17, %18, %19, %20, %21, %22, %23, %24, %25, %26, %27, %28, %29, %30, %31, %32, %33, %34, %35, %36, %37, %38, %39, %40, %41, %42, %43, %44, %45, %46, %47, %48, %49, %50, %51, %52, %53, %54, %55, %56, %57, %58, %59, %60, %61, %62, %63}, "
        "{%64, %65, %66, %67}, %68, p, 1, 1, 1;\n}\n"
        : "+f"(d[0]), "+f"(d[1]), "+f"(d[2]), "+f"(d[3]), "+f"(d[4]), "+f"(d[5]), "+f"(d[6]), "+f"(d[7]), "+f"(d[8]), "+f"(d[9]), "+f"(d[10]), "+f"(d[11]), "+f"(d[12]), "+f"(d[13]), "+f"(d[14]), "+f"(d[15]), "+f"(d[16]), "+f"(d[17]), "+f"(d[18]), "+f"(d[19]), "+f"(d[20]), "+f"(d[21]), "+f"(d[22]), "+f"(d[23]), "+f"(d[24]), "+f"(d[25]), "+f"(d[26]), "+f"(d[27]), "+f"(d[28]), "+f"(d[29]), "+f"(d[30]), "+f"(d[31]), "+f"(d[32]), "+f"(d[33]), "+f"(d[34]), "+f"(d[35]), "+f"(d[36]), "+f"(d[37]), "+f"(d[38]), "+f"(d[39]), "+f"(d[40]), "+f"(d[41]), "+f"(d[42]), "+f"(d[43]), "+f"(d[44]), "+f"(d[45]), "+f"(d[46]), "+f"(d[47]), "+f"(d[48]), "+f"(d[49]), "+f"(d[50]), "+f"(d[51]), "+f"(d[52]), "+f"(d[53]), "+f"(d[54]), "+f"(d[55]), "+f"(d[56]), "+f"(d[57]), "+f"(d[58]), "+f"(d[59]), "+f"(d[60]), "+f"(d[61]), "+f"(d[62]), "+f"(d[63])
        : "r"(a0), "r"(a1), "r"(a2), "r"(a3), "l"(db), "r"(scale_d));
}

template <int OFF> __device__ __forceinline__ void wgmma_rs_n64_tb(float (&d)[64], uint32_t a0, uint32_t a1, uint32_t a2, uint32_t a3, uint64_t db, int scale_d) {
    asm volatile("{\n.reg .pred p;\nsetp.ne.b32 p, %37, 0;\n"
        "wgmma.mma_async.sync.aligned.m64n64k16.f32.bf16.bf16 "
        "{%0, %1, %2, %3, %4, %5, %6, %7, %8, %9, %10, %11, %12, %13, %14, %15, %16, %17, %18, %19, %20, %21, %22, %23, %24, %25, %26, %27, %28, %29, %30, %31}, "
        "{%32, %33, %34, %35}, %36, p, 1, 1, 1;\n}\n"
        : "+f"(d[OFF + 0]), "+f"(d[OFF + 1]), "+f"(d[OFF + 2]), "+f"(d[OFF + 3]), "+f"(d[OFF + 4]), "+f"(d[OFF + 5]), "+f"(d[OFF + 6]), "+f"(d[OFF + 7]), "+f"(d[OFF + 8]), "+f"(d[OFF + 9]), "+f"(d[OFF + 10]), "+f"(d[OFF + 11]), "+f"(d[OFF + 12]), "+f"(d[OFF + 13]), "+f"(d[OFF + 14]), "+f"(d[OFF + 15]), "+f"(d[OFF + 16]), "+f"(d[OFF + 17]), "+f"(d[OFF + 18]), "+f"(d[OFF + 19]), "+f"(d[OFF + 20]), "+f"(d[OFF + 21]), "+f"(d[OFF + 22]), "+f"(d[OFF + 23]), "+f"(d[OFF + 24]), "+f"(d[OFF + 25]), "+f"(d[OFF + 26]), "+f"(d[OFF + 27]), "+f"(d[OFF + 28]), "+f"(d[OFF + 29]), "+f"(d[OFF + 30]), "+f"(d[OFF + 31])
        : "r"(a0), "r"(a1), "r"(a2), "r"(a3), "l"(db), "r"(scale_d));
}

__device__ __forceinline__ void wgmma_ss_n32_ta(float (&d)[16], uint64_t da, uint64_t db, int scale_d) {
    asm volatile("{\n.reg .pred p;\nsetp.ne.b32 p, %18, 0;\n"
        "wgmma.mma_async.sync.aligned.m64n32k16.f32.bf16.bf16 "
        "{%0, %1, %2, %3, %4, %5, %6, %7, %8, %9, %10, %11, %12, %13, %14, %15}, "
        "%16, %17, p, 1, 1, 1, 0;\n}\n"
        : "+f"(d[0]), "+f"(d[1]), "+f"(d[2]), "+f"(d[3]), "+f"(d[4]), "+f"(d[5]), "+f"(d[6]), "+f"(d[7]), "+f"(d[8]), "+f"(d[9]), "+f"(d[10]), "+f"(d[11]), "+f"(d[12]), "+f"(d[13]), "+f"(d[14]), "+f"(d[15])
        : "l"(da), "l"(db), "r"(scale_d));
}

__device__ __forceinline__ void wgmma_rs_n32(float (&d)[16], uint32_t a0, uint32_t a1, uint32_t a2, uint32_t a3, uint64_t db, int scale_d) {
    asm volatile("{\n.reg .pred p;\nsetp.ne.b32 p, %21, 0;\n"
        "wgmma.mma_async.sync.aligned.m64n32k16.f32.bf16.bf16 "
        "{%0, %1, %2, %3, %4, %5, %6, %7, %8, %9, %10, %11, %12, %13, %14, %15}, "
        "{%16, %17, %18, %19}, %20, p, 1, 1, 0;\n}\n"
        : "+f"(d[0]), "+f"(d[1]), "+f"(d[2]), "+f"(d[3]), "+f"(d[4]), "+f"(d[5]), "+f"(d[6]), "+f"(d[7]), "+f"(d[8]), "+f"(d[9]), "+f"(d[10]), "+f"(d[11]), "+f"(d[12]), "+f"(d[13]), "+f"(d[14]), "+f"(d[15])
        : "r"(a0), "r"(a1), "r"(a2), "r"(a3), "l"(db), "r"(scale_d));
}

__device__ __forceinline__ uint64_t pack4(float a, float b, float c, float d, uint32_t par) {
    const uint32_t r = ((__float_as_uint(a) + ((par ^ 1) << 16)) & 0xfffe0000u) | (par << 16);
    return (uint64_t)__byte_perm(r, pack_bf16(a, b), 0x7632) | ((uint64_t)pack_bf16(c, d) << 32);
}
__device__ __forceinline__ void st_part(uint64_t* p, unsigned int* cnt, const float (&a)[16], uint32_t ep, int lane) {
    const uint32_t par = ep & 1;
#pragma unroll
    for (int j = 0; j < 4; j++)
        asm volatile("st.relaxed.gpu.global.b64 [%0], %1;" :: "l"(p + j * 32), "l"(pack4(a[4 * j], a[4 * j + 1], a[4 * j + 2], a[4 * j + 3], par)) : "memory");
    cnt_inc(cnt, lane == 0);
}
__device__ __forceinline__ void ldsm_t4(uint32_t (&r)[4], uint32_t addr) {
    asm volatile("ldmatrix.sync.aligned.m8n8.x4.trans.shared.b16 {%0, %1, %2, %3}, [%4];"
                 : "=r"(r[0]), "=r"(r[1]), "=r"(r[2]), "=r"(r[3]) : "r"(addr) : "memory");
}

struct Maps { CUtensorMap k, v, vh, x, wq, wo; const unsigned char *wop, *kp, *vp, *outp, *wqp; };

__device__ __forceinline__ void sts32(uint32_t a, uint32_t v) { asm volatile("st.shared.u32 [%0], %1;" :: "r"(a), "r"(v) : "memory"); }
__device__ __forceinline__ uint32_t gtime32() { uint32_t t; asm volatile("mov.u32 %0, %%globaltimer_lo;" : "=r"(t)); return t; }
__device__ __forceinline__ void produce(const Maps& mp, int i0, int i1, uint32_t sb, int rank, int row8) {
    const uint32_t bars = sb + OFF_BAR;
#pragma unroll 1
    for (int i = i0; i < i1; i++) {
        const unsigned int e = lds32(sb + OFF_TAB + 256 + 4 * i);
        const uint32_t dst = sb + (e & 15) * U, fb = bars + 8 * ((e >> 4) & 31);
        const int type = (e >> 9) & 7, tile = (e >> 12) & 31;
        const int rt = (tile + ((row8 >> 10) * 5)) & 31;
        if ((e >> 23) & 1) mbar_wait(bars + 8 * ((e >> 17) & 31), (e >> 22) & 1);
        if (type < 2 || type == 5) GT_(128 + (type ? 32 : 0) + tile);
        if (type < 2 || type == 5) {
            const uint32_t t0 = lds32(sb + OFF_EP + 4), due = 50 + (((e >> 24) * (1400 * 32 + (2 * (row8 >> 13) - 7) * (0 / 2))) >> 6);
            for (int n = 0; n < 4096 && gtime32() - t0 < due; n++) {}
        }
        if (type < 2 || type == 5) GT_((type ? 32 : 0) + tile);
        if (type == 0) {
            mbar_expect_tx(fb, 2 * U);
            tma4d_mc(dst + rank * U, &mp.k, fb, row8 + rt * 8 + rank * 4);
        } else if (type == 1) {
            mbar_expect_tx(fb, U);
            tma_v(dst, &mp.v, fb, (row8 + rt * 8) * 8, 0, rank);
        } else if (type == 5) {
            const uint32_t fb2 = 1 && tile == 31 ? fb + 8 : fb;
            if (fb2 != fb) { mbar_expect_tx(fb, U / 2); mbar_expect_tx(fb2, U / 2); } else mbar_expect_tx(fb, U);
            const int r0 = rt - tile + 28 + (tile & 1) * 2, c1 = (tile >> 1) & 1;
            tma_v(dst, &mp.vh, fb, (row8 + (r0 & 31) * 8) * 8, c1, rank);
            tma_v(dst + 8192, &mp.vh, fb2, (row8 + ((r0 + 1) & 31) * 8) * 8, c1, rank);
        } else if (type == 3) {
            const int fc_ = fresh_cta();
            const unsigned int* pf = g_pcnt + (fc_ >> 4) * 28 * 32;
            const int R = ((fc_ >> 1) & 7) * 6, blk4 = ((fc_ & 1) ^ 1) * 16;
            prefetch_l2(pf + (blk4 + (R >> 2)) * 32);
            prefetch_l2(pf + (blk4 + ((R + 5) >> 2)) * 32);
            prefetch_l2(pf + (12 + ((fc_ & 15) >> 2)) * 32);
        } else {
            const int col = (tile == 6 ? 3 : rank * 4 + ((0x2121 >> (4 * tile)) & 3)) * 64, c0 = rank ^ ((0x2c >> tile) & 1);
            const int g4 = ((row8 >> 10) & 7) * 4;
            if (type == 2) {
                mbar_expect_tx(fb, 2 * U);
                tma_wo(dst, &mp.wo, fb, col, c0, g4);
            } else if (((row8 >> 13) & 3) == 0) {
                asm volatile("cp.async.bulk.prefetch.tensor.4d.L2.global [%0, {%1, %2, %3, %4}];" :: "l"(&mp.wo), "r"(col), "r"(0), "r"(c0), "r"(g4) : "memory");
            }
        }
    }
}

__device__ __forceinline__ void scale_p(uint32_t (&p)[16], float f0, float f1) {
    const uint32_t h0 = pack_bf16(f0, f0), h1 = pack_bf16(f1, f1);
    const float r0 = f0 - __uint_as_float(h0 << 16), r1 = f1 - __uint_as_float(h1 << 16);
    const uint32_t l0 = pack_bf16(r0, r0), l1 = pack_bf16(r1, r1);
#pragma unroll
    for (int i = 0; i < 16; i++) {
        uint32_t t;
        asm("mul.rn.bf16x2 %0, %1, %2;" : "=r"(t) : "r"(p[i]), "r"((i & 1) ? l1 : l0));
        asm("fma.rn.bf16x2 %0, %1, %2, %3;" : "=r"(p[i]) : "r"(p[i]), "r"((i & 1) ? h1 : h0), "r"(t));
    }
}
__device__ __forceinline__ void softmax_tile(const float (&s)[32], float& m0, float& m1, float& l0, float& l1, float& a0, float& a1,
                                             uint32_t (&pa)[16], float cs) {
    float x0 = fmaxf(s[0], s[1]), x1 = fmaxf(s[2], s[3]);
#pragma unroll
    for (int i = 1; i < 8; i++) {
        x0 = fmaxf(x0, fmaxf(s[4 * i], s[4 * i + 1]));
        x1 = fmaxf(x1, fmaxf(s[4 * i + 2], s[4 * i + 3]));
    }
    x0 = fmaxf(x0, __shfl_xor_sync(0xffffffffu, x0, 1)); x1 = fmaxf(x1, __shfl_xor_sync(0xffffffffu, x1, 1));
    x0 = fmaxf(x0, __shfl_xor_sync(0xffffffffu, x0, 2)); x1 = fmaxf(x1, __shfl_xor_sync(0xffffffffu, x1, 2));
    const float n0 = fmaxf(m0, x0), n1 = fmaxf(m1, x1);
    a0 = ex2((m0 - n0) * cs); a1 = ex2((m1 - n1) * cs);
    m0 = n0; m1 = n1;
    const float mc0 = n0 * cs, mc1 = n1 * cs;
    float r0 = 0.f, r1 = 0.f;
#pragma unroll
    for (int i = 0; i < 8; i++) {
        const float e0 = ex2(fmaf(s[4 * i], cs, -mc0)), e1 = ex2(fmaf(s[4 * i + 1], cs, -mc0));
        const float e2 = ex2(fmaf(s[4 * i + 2], cs, -mc1)), e3 = ex2(fmaf(s[4 * i + 3], cs, -mc1));
        r0 += e0 + e1; r1 += e2 + e3;
        pa[2 * i] = pack_bf16(e0, e1); pa[2 * i + 1] = pack_bf16(e2, e3);
    }
    l0 = l0 * a0 + r0; l1 = l1 * a1 + r1;
}

__global__ void __cluster_dims__(2, 1, 1) __launch_bounds__(256, 1)
fused_kernel(const __grid_constant__ Maps mp, __nv_bfloat16* __restrict__ out) {
    extern __shared__ __align__(1024) unsigned char smem[];
    const uint32_t sb = smem_u32(smem);
    const uint32_t bars = sb + OFF_BAR;
    const int tid = threadIdx.x, wg = tid >> 7, warp = (tid >> 5) & 3, lane = tid & 31;
    const int rank = blockIdx.x & 1, grp = blockIdx.x >> 1, b = grp >> 3, hkv = grp & 7;
    const int row8 = (grp * SK + (SK - WIN)) >> 3;
    const int bq = b >> 2, p = b & 3;

    if (0 == 1 && tid < 224) prefetch_l2(mp.wqp + (size_t)(bq * 224 + tid) * 8192 + (hkv * 512 + p * 128 + rank * 64) * 2);
    if (0 == 2 && tid < 224) touch_l2(mp.wqp + (size_t)(bq * 224 + tid) * 8192 + (hkv * 512 + p * 128 + rank * 64) * 2);
    if (0 == 3 && tid < 224) { touch_l2(mp.wqp + (size_t)(tid * 2 + bq) * 8192 + (hkv * 512 + p * 128 + rank * 64) * 2); }
    if (3 == 10 && tid < 224) prefetch_l2(mp.wop + blockIdx.x * 28672 + tid * 128);
    if (3 == 11 && tid < 224) touch_l2(mp.wop + blockIdx.x * 28672 + tid * 128);
    if (3 == 9 && tid == 224)
        asm volatile("cp.async.bulk.prefetch.L2.global [%0], %1;" :: "l"(mp.wop + blockIdx.x * 28672), "r"(28672) : "memory");
    if (0 && tid == 232) {
        const size_t r0 = (size_t)(row8 + ((grp * 5) & 31) * 8) * 4096 + rank * 16384;
        if (0 & 1) asm volatile("cp.async.bulk.prefetch.L2.global.L2::cache_hint [%0], %1, %2;" :: "l"(mp.kp + r0), "r"(16384), "l"(EVF) : "memory");
        if (0 & 2) asm volatile("cp.async.bulk.prefetch.L2.global.L2::cache_hint [%0], %1, %2;" :: "l"(mp.vp + r0), "r"(16384), "l"(EVF) : "memory");
    }
    {
        const int w8 = tid >> 5;
        const int qrot = 0;
        if (wg) CK_(44);
        if (lane == 0) {
            if (w8 == 4) {
                for (int i = 0; i < KE; i++) mbar_init(bars + 8 * i, 1);
                for (int i = KE; i < VE; i++) mbar_init(bars + 8 * i, 8);
                mbar_init(bars + 8 * PB, 1);
            } else if (w8 == 5) {
                for (int i = SF; i < SFREE; i++) mbar_init(bars + 8 * i, 1);
            } else if (w8 == 3) {
                for (int i = VE; i < PB; i++) mbar_init(bars + 8 * i, 4);
                for (int i = WF; i < SF; i++) mbar_init(bars + 8 * i, 1);
                mbar_init(bars + 8 * SFREE, 2);
                mbar_init(bars + 8 * QRDY, 4);
            }
        }
        __syncwarp();
        if (wg) CK_(45);
        asm volatile("fence.mbarrier_init.release.cluster;" ::: "memory");
        asm volatile("barrier.cluster.arrive.relaxed.aligned;" ::: "memory");
        if (wg) CK_(46);
        if (tid == 128) {
            asm volatile("st.shared.u32 [%0], %1;" :: "r"(sb + OFF_EP + 4), "r"(gtime32()) : "memory");
            mbar_expect_tx(bars + 8 * KF, 2 * U);
            mbar_expect_tx(bars + 8 * VF, U);
            if (0) tma_v(sb + 2 * U, &mp.v, bars + 8 * VF, (row8 + ((grp * 5) & 31) * 8) * 8, 0, rank);
            mbar_expect_tx(bars + 8 * PA, 8192);
            mbar_expect_tx(bars + 8 * PB, 8192);
        }
        if (tid == 160) {
            if (sb & 1023) __trap();
            const int xrow = (bq * 4 + 2 * rank) * SQ;
            for (int c = 0; c < 7; c++) {
                mbar_expect_tx(bars + 8 * (SF + c), 8192 + U);
                if (c < 2) {
                    tma2d(sb + OFF_WQ + c * U, &mp.wq, bars + 8 * (SF + c), hkv * 512 + p * 128, (c + qrot) % 7 * 64);
                    tma2d(sb + OFF_WQ + c * U + 8192, &mp.wq, bars + 8 * (SF + c), hkv * 512 + p * 128 + 64, (c + qrot) % 7 * 64);
                }
                tma2d(sb + OFF_X + c * 8192, &mp.x, bars + 8 * (SF + c), (c + qrot) % 7 * 64, xrow);
            }
        }
        if (tid < 36) {
            const uint4 v = __ldg((const uint4*)&g_sched + tid);
            asm volatile("st.shared.v4.b32 [%0], {%1, %2, %3, %4};" :: "r"(sb + OFF_TAB + tid * 16), "r"(v.x), "r"(v.y), "r"(v.z), "r"(v.w) : "memory");
        }
        if (tid == 224) {
            prefetch_l2(g_qcnt + (grp * 4 + rank * 2) * 32); prefetch_l2(g_qcnt + (grp * 4 + rank * 2 + 1) * 32);
            const uint32_t e = ld_relaxed32(g_epoch + blockIdx.x * 8) + 1;
            asm volatile("st.shared.u32 [%0], %1;" :: "r"(sb + OFF_EP), "r"(e) : "memory");
            g_epoch[blockIdx.x * 8] = e;
        }
        __syncwarp();
        asm volatile("barrier.cluster.wait.aligned;" ::: "memory");
        if (wg) CK_(48);
        if (tid == 128) {
            const int wcol = hkv * 512 + p * 128 + rank * 64;
            for (int c = 2; c < 7; c++) tma2d_mc(sb + OFF_WQ + c * U + rank * 8192, &mp.wq, bars + 8 * (SF + c), wcol, (c + qrot) % 7 * 64);
            CK_(49);
            tma4d_mc(sb + rank * U, &mp.k, bars + 8 * KF, row8 + ((grp * 5) & 31) * 8 + rank * 4);
            if (!0) tma_v(sb + 2 * U, &mp.v, bars + 8 * VF, (row8 + ((grp * 5) & 31) * 8) * 8, 0, rank);
            CK_(50);
        }
    }
    __syncwarp();

    {
        float acc[32];
#pragma unroll
        for (int c = 0; c < 7; c++) {
            mbar_wait(bars + 8 * (SF + c), 0);
            if (wg == 0) CK_(51 + c);
            if (c == -1 && tid == 192) {
                const size_t r1 = (size_t)(row8 + ((grp * 5 + 1) & 31) * 8) * 4096 + rank * 16384;
                asm volatile("cp.async.bulk.prefetch.L2.global.L2::cache_hint [%0], %1, %2;" :: "l"(mp.kp + r1), "r"(16384), "l"(EVF) : "memory");
                asm volatile("cp.async.bulk.prefetch.L2.global.L2::cache_hint [%0], %1, %2;" :: "l"(mp.vp + r1), "r"(16384), "l"(EVF) : "memory");
            }
            if (c == 3 && tid == 160)
                asm volatile("cp.async.bulk.prefetch.L2.global [%0], %1;" :: "l"(mp.wop + blockIdx.x * 28672), "r"(28672) : "memory");
            const uint64_t da = make_desc(sb + OFF_X + c * 8192, 16, 1024);
            const uint64_t db = make_desc(sb + OFF_WQ + c * U + wg * 8192, 8192, 1024);
            wg_fence();
#pragma unroll
            for (int k = 0; k < 4; k++) wgmma_ss_n64_tb(acc, da + k * 2, db + k * 128, c + k);
            wg_commit();
        }
        wg_wait<0>();
        reg_fence(acc);
        if (wg == 0) CK_(58);
        const int bb = bq * 4 + 2 * rank + (warp >> 1);
        uint4* dst = g_q + ((size_t)(bb * 8 + hkv) * 16 + (p & 1) * 8 + wg * 4) * 128 + ((p >> 1) * 2 + (warp & 1)) * 32 + lane;
#pragma unroll
        for (int s = 0; s < 4; s++)
            st_relaxed(dst + s * 128, ~pack_bf16(acc[8 * s], acc[8 * s + 1]), ~pack_bf16(acc[8 * s + 2], acc[8 * s + 3]),
                       ~pack_bf16(acc[8 * s + 4], acc[8 * s + 5]), ~pack_bf16(acc[8 * s + 6], acc[8 * s + 7]));
        cnt_inc(g_qcnt + ((bb * 8 + hkv) * 4 + (p >> 1) * 2 + (warp & 1)) * 32, lane == 0);
        if (wg == 0) CK_(59);
        bar_sync(1, 256);
    }

    if (wg == 0) {
        uint32_t qf[64];
        {
            const uint4* src = g_q + (size_t)grp * 16 * 128 + tid;
            uint4 v[16];
            cnt_wait(g_qcnt + (grp * 4 + warp) * 32, lds32(sb + OFF_EP) * 4, lane);
            CK_(60);
            for (uint32_t n = 0;; n++) {
#pragma unroll
                for (int i = 0; i < 16; i++) v[i] = ld_relaxed(src + i * 128);
                bool ok = true;
#pragma unroll
                for (int i = 0; i < 16; i++) ok = ok && valid(v[i]);
                if (__all_sync(0xffffffffu, ok)) break;
                if (n > (1u << 20)) TIMEOUT(43)
            }
            mbar_arrive_pred(bars + 8 * QRDY, lane == 0);
#pragma unroll
            for (int i = 0; i < 16; i++) { qf[4 * i] = ~v[i].x; qf[4 * i + 1] = ~v[i].y; qf[4 * i + 2] = ~v[i].z; qf[4 * i + 3] = ~v[i].w; }
            __syncwarp();
        }
        CK_(61);
        if (tid == 0) STAMP(2);
        if (tid == 0) STAMP2(0);
        float o[64], s[32];
#pragma unroll
        for (int i = 0; i < 64; i++) o[i] = 0.f;
        float m0 = -INFINITY, m1 = -INFINITY, l0 = 0.f, l1 = 0.f, a0, a1;
        uint32_t pa[16];
        const float cs = 0.0625f * 1.4426950408889634f;
        const uint32_t rbars = mapa(bars, rank ^ 1);
        {
            constexpr unsigned int e = SC.kc[0];
            mbar_wait(bars + 8 * ((e >> 8) & 31), (e >> 13) & 1);
            const uint64_t dk = make_desc(sb + (e & 255) * U, 16, 4096);
            reg_fence(qf); reg_fence(s);
            wg_fence();
#pragma unroll
            for (int k = 0; k < 16; k++)
                wgmma_rs_n64(s, qf[4 * k], qf[4 * k + 1], qf[4 * k + 2], qf[4 * k + 3], dk + (k >> 2) * 64 + (k & 3) * 2, k);
            wg_commit();
            wg_wait<0>();
            reg_fence(s);
            if (lane == 0) { mbar_arrive(bars + 8 * ((e >> 14) & 31)); mbar_arrive_remote(rbars + 8 * ((e >> 14) & 31)); }
            softmax_tile(s, m0, m1, l0, l1, a0, a1, pa, cs);
        }
#pragma unroll 1
        for (int t = 0; t < NT - 4; t++) {
            const unsigned int ek = lds32(sb + OFF_TAB + 4 + 4 * t), ev = lds32(sb + OFF_TAB + 128 + 4 * t);
            TIC();
            mbar_wait(bars + 8 * ((ek >> 8) & 31), (ek >> 13) & 1);
            if (tid == 0) GT_(64 + t + 1);
            const uint64_t dk = make_desc(sb + (ek & 255) * U, 16, 4096);
            reg_fence(qf); reg_fence(s);
            wg_fence();
#pragma unroll
            for (int k = 0; k < 16; k++)
                wgmma_rs_n64(s, qf[4 * k], qf[4 * k + 1], qf[4 * k + 2], qf[4 * k + 3], dk + (k >> 2) * 64 + (k & 3) * 2, k);
            wg_commit();
            if (tid == 0 && (t & 7) == 7 && t < 16) STAMP(10 + (t >> 3));
            if (t == RK) {
                uint4* src = g_q + ((size_t)grp * 16 + rank * 8) * 128 + tid;
#pragma unroll
                for (int i = 0; i < 8; i++) st_relaxed(src + i * 128, 0, 0, 0, 0);
            }
            if (__any_sync(0xffffffffu, (a0 != 1.f) || (a1 != 1.f))) {
#pragma unroll
                for (int i = 0; i < 16; i++) { o[4 * i] *= a0; o[4 * i + 1] *= a0; o[4 * i + 2] *= a1; o[4 * i + 3] *= a1; }
            }
            wg_wait<0>();
            reg_fence(s);
            mbar_arrive2_pred(bars + 8 * ((ek >> 14) & 31), rbars + 8 * ((ek >> 14) & 31), lane == 0 && ((ek >> 19) & 1));
            TIC();
            mbar_wait(bars + 8 * ((ev >> 8) & 31), (ev >> 13) & 1);
            if (tid == 0) GT_(96 + t);
            const uint64_t dv = make_desc(sb + (ev & 255) * U, 8192, 1024);
            reg_fence(o); reg_fence(pa);
            wg_fence();
#pragma unroll
            for (int k = 0; k < 4; k++)
                wgmma_rs_n128_tb(o, pa[4 * k], pa[4 * k + 1], pa[4 * k + 2], pa[4 * k + 3], dv + k * 128, 1);
            wg_commit();
            uint32_t pn[16];
            softmax_tile(s, m0, m1, l0, l1, a0, a1, pn, cs);
            reg_fence(pn);
            wg_wait<0>();
            reg_fence(o); reg_fence(pa);
            mbar_arrive_pred(bars + 8 * ((ev >> 14) & 31), lane == 0 && ((ev >> 19) & 1));
#pragma unroll
            for (int i = 0; i < 16; i++) pa[i] = pn[i];
        }
        uint32_t pb[16], pn[16], pc[16];
        float b0 = 1.f, b1 = 1.f, c0 = 1.f, c1 = 1.f;
        const float d0 = a0, d1 = a1;
#pragma unroll
        for (int u = NT - 3; u < NT; u++) {
            const unsigned int ek = SC.kc[u];
            mbar_wait(bars + 8 * ((ek >> 8) & 31), (ek >> 13) & 1);
            if (tid == 0 && u == 31) STAMP(3);
            if (u == 31) CK_(0);
            const uint64_t dk = make_desc(sb + (ek & 255) * U, 16, 4096);
            reg_fence(qf); reg_fence(s);
            wg_fence();
#pragma unroll
            for (int k = 0; k < 16; k++)
                wgmma_rs_n64(s, qf[4 * k], qf[4 * k + 1], qf[4 * k + 2], qf[4 * k + 3], dk + (k >> 2) * 64 + (k & 3) * 2, k);
            wg_commit();
            if (u < NT - 1) {
                const uint32_t stash = sb + OFF_PO + (u - (NT - 3)) * 8192 + tid * 16;
#pragma unroll
                for (int i = 0; i < 4; i++)
                    asm volatile("st.shared.v4.b32 [%0], {%1, %2, %3, %4};" :: "r"(stash + i * 2048), "r"(pa[4 * i]), "r"(pa[4 * i + 1]), "r"(pa[4 * i + 2]), "r"(pa[4 * i + 3]) : "memory");
            }
            wg_wait<0>();
            reg_fence(s); reg_fence(qf);
            if (u == 31) CK_(1);
            if ((ek >> 19) & 1) mbar_arrive2_pred(bars + 8 * ((ek >> 14) & 31), rbars + 8 * ((ek >> 14) & 31), lane == 0);
            if (u == NT - 1) mbar_arrive_pred(bars + 8 * QRDY, lane == 0);
            if (u == NT - 3) softmax_tile(s, m0, m1, l0, l1, a0, a1, pa, cs);
            else if (u == NT - 2) softmax_tile(s, m0, m1, l0, l1, a0, a1, pb, cs);
            else softmax_tile(s, m0, m1, l0, l1, a0, a1, pn, cs);
            c0 *= a0; c1 *= a1;
            if (u > NT - 3) { b0 *= a0; b1 *= a1; }
        }
        const int ft = fresh_tid();
#pragma unroll
        for (int i = 0; i < 4; i++) {
            asm volatile("ld.shared.v4.b32 {%0, %1, %2, %3}, [%4];" : "=r"(pa[4 * i]), "=r"(pa[4 * i + 1]), "=r"(pa[4 * i + 2]), "=r"(pa[4 * i + 3])
                         : "r"(sb + OFF_PO + ft * 16 + i * 2048) : "memory");
            asm volatile("ld.shared.v4.b32 {%0, %1, %2, %3}, [%4];" : "=r"(pc[4 * i]), "=r"(pc[4 * i + 1]), "=r"(pc[4 * i + 2]), "=r"(pc[4 * i + 3])
                         : "r"(sb + OFF_PO + 8192 + ft * 16 + i * 2048) : "memory");
        }
        {
            const float e0 = c0 * d0, e1 = c1 * d1;
#pragma unroll
            for (int i = 0; i < 16; i++) { o[4 * i] *= e0; o[4 * i + 1] *= e0; o[4 * i + 2] *= e1; o[4 * i + 3] *= e1; }
        }
        if (__any_sync(0xffffffffu, (c0 != 1.f) || (c1 != 1.f))) {
            scale_p(pa, c0, c1); scale_p(pc, b0, b1); scale_p(pb, a0, a1);
        }
        reg_fence(pa); reg_fence(pc);
        __syncwarp();
        mbar_arrive2_pred(bars + 8 * (KE + 31 % RK), rbars + 8 * (KE + 31 % RK), (ft & 31) == 0);
        const uint32_t obuf = sb + OUN * U;
        const uint64_t dob = make_desc(obuf, 16, 1024), dpo = make_desc(sb + OFF_PO, 16, 1024);
        const int g = (ft >> 2) & 7;
        const uint32_t obase = obuf + (ft >> 6) * 4096 + (((ft >> 5) & 1) * 16 + g) * 128 + (ft & 3) * 4;
        float ay[16], az[16];
        uint32_t gy[8][4], gz[8][4], hy[8][4], hz[8][4];
        const uint32_t wad = sb + (((ft >> 4) & 1) * 8 + (ft & 7)) * 128 + (((((ft >> 4) & 6) + ((ft >> 3) & 1)) ^ (ft & 7)) << 4);
        const uint64_t dw0 = make_desc(sb + 10 * U, 16, 1024), dw1 = dw0 + 2 * U / 16, dw2 = dw0 - 5 * U / 16, dw3 = dw0 - 10 * U / 16;
        static_assert(SC.wun[0] == 10 && SC.wun[1] == 12 && SC.wun[2] == 5 && SC.wun[3] == 0, "");
        {
            constexpr unsigned int ev = SC.vc[NT - 4], ew = SC.vc[NT - 3];
            CK_(2); CKF_(20, SC.vc[NT - 4]); CKF_(21, SC.vc[NT - 3]);
            mbar_wait(bars + 8 * ((ev >> 8) & 31), (ev >> 13) & 1);
            const uint64_t dv = make_desc(sb + (ev & 255) * U, 8192, 1024), dv2 = make_desc(sb + (ew & 255) * U, 8192, 1024);
            reg_fence(o); reg_fence(pa); reg_fence(pb); reg_fence(pn); reg_fence(pc);
            wg_fence();
#pragma unroll
            for (int k = 0; k < 4; k++) wgmma_rs_n64_tb<0>(o, pa[4 * k], pa[4 * k + 1], pa[4 * k + 2], pa[4 * k + 3], dv + k * 128, 1);
#pragma unroll
            for (int k = 0; k < 4; k++) wgmma_rs_n64_tb<0>(o, pc[4 * k], pc[4 * k + 1], pc[4 * k + 2], pc[4 * k + 3], dv + 512 + k * 128, 1);
            wg_commit();
            l0 += __shfl_xor_sync(0xffffffffu, l0, 1); l1 += __shfl_xor_sync(0xffffffffu, l1, 1);
            l0 += __shfl_xor_sync(0xffffffffu, l0, 2); l1 += __shfl_xor_sync(0xffffffffu, l1, 2);
            l0 = 1.0f / l0; l1 = 1.0f / l1;
            mbar_wait(bars + 8 * (WF + 0), 0);
            mbar_wait(bars + 8 * (WF + 1), 0);
#pragma unroll
            for (int k = 0; k < 8; k++) {
                ldsm_t4(gy[k], wad + 10 * U + ((k >> 2) * 8 + 4 + (k & 3)) * 2048);
                ldsm_t4(gz[k], wad + 12 * U + ((k >> 2) * 8 + 4 + (k & 3)) * 2048);
            }
            bar_sync(5, 128);
            mbar_wait(bars + 8 * ((ew >> 8) & 31), (ew >> 13) & 1);
            CK_(3);
            wg_fence();
#pragma unroll
            for (int k = 0; k < 4; k++) wgmma_rs_n64_tb<0>(o, pb[4 * k], pb[4 * k + 1], pb[4 * k + 2], pb[4 * k + 3], dv2 + k * 128, 1);
#pragma unroll
            for (int k = 0; k < 4; k++) wgmma_rs_n64_tb<0>(o, pn[4 * k], pn[4 * k + 1], pn[4 * k + 2], pn[4 * k + 3], dv2 + 512 + k * 128, 1);
            wg_commit();
            wg_wait<0>();
            reg_fence(o);
            CK_(4); CKF_(22, SC.vc[NT - 1]);
#pragma unroll
            for (int j = 0; j < 8; j++) {
                const uint32_t ad = obase + ((j ^ g) << 4);
                asm volatile("st.shared.b32 [%0], %1;" :: "r"(ad), "r"(pack_bf16(o[4 * j] * l0, o[4 * j + 1] * l0)) : "memory");
                asm volatile("st.shared.b32 [%0], %1;" :: "r"(ad + 1024), "r"(pack_bf16(o[4 * j + 2] * l1, o[4 * j + 3] * l1)) : "memory");
            }
            fence_async();
            CK_(5);
            bar_sync(2, 256);
            CK_(6); CKF_(23, SC.vc[NT - 1]);
            CK_(28);
            wg_fence();
#pragma unroll
            for (int k = 0; k < 8; k++) wgmma_ss_n32_ta(ay, dw0 + (k >> 2) * 1024 + (k & 3) * 128, dob + (k >> 2) * 256 + (k & 3) * 2, k);
#pragma unroll
            for (int k = 0; k < 8; k++) wgmma_ss_n32_ta(az, dw1 + (k >> 2) * 1024 + (k & 3) * 128, dob + (k >> 2) * 256 + (k & 3) * 2, k);
            wg_commit();
            CK_(7); CKF_(24, SC.vc[NT - 1]);
        }
        const int fc_ = fresh_cta(), lane = ft & 31;
        uint64_t* part; unsigned int* pcnt; uint32_t ep;
        {
            constexpr unsigned int ev = SC.vc[NT - 1], ew = SC.vc[NT - 2];
            const uint64_t dv = make_desc(sb + (ev & 255) * U, 8192, 1024), dv2 = make_desc(sb + (ew & 255) * U, 8192, 1024);
            mbar_wait(bars + 8 * ((ew >> 8) & 31), (ew >> 13) & 1);
            wg_fence();
#pragma unroll
            for (int k = 0; k < 4; k++) wgmma_rs_n64_tb<32>(o, pa[4 * k], pa[4 * k + 1], pa[4 * k + 2], pa[4 * k + 3], dv2 + k * 128, 1);
#pragma unroll
            for (int k = 0; k < 4; k++) wgmma_rs_n64_tb<32>(o, pc[4 * k], pc[4 * k + 1], pc[4 * k + 2], pc[4 * k + 3], dv2 + 512 + k * 128, 1);
            wg_commit();
            CK_(26); CKF_(27, SC.vc[NT - 1]);
            mbar_wait(bars + 8 * ((ev >> 8) & 31), (ev >> 13) & 1);
            CK_(9); if (ft == 0) GT_(95);
            if (tid == 0) STAMP(4);
            wg_fence();
#pragma unroll
            for (int k = 0; k < 4; k++) wgmma_rs_n64_tb<32>(o, pb[4 * k], pb[4 * k + 1], pb[4 * k + 2], pb[4 * k + 3], dv + k * 128, 1);
            wg_commit();
            mbar_wait(bars + 8 * ((ev >> 8) & 31) + 8, (ev >> 13) & 1);
            wg_fence();
#pragma unroll
            for (int k = 0; k < 4; k++) wgmma_rs_n64_tb<32>(o, pn[4 * k], pn[4 * k + 1], pn[4 * k + 2], pn[4 * k + 3], dv + 512 + k * 128, 1);
            wg_commit();
            wg_wait<0>();
            reg_fence(o); reg_fence(pb); reg_fence(pn); reg_fence(ay); reg_fence(az);
            reg_fence(pa); reg_fence(pc);
            CK_(10);
#pragma unroll
            for (int j = 8; j < 16; j++) {
                const uint32_t ad = obase + 8192 + (((j & 7) ^ g) << 4);
                asm volatile("st.shared.b32 [%0], %1;" :: "r"(ad), "r"(pack_bf16(o[4 * j] * l0, o[4 * j + 1] * l0)) : "memory");
                asm volatile("st.shared.b32 [%0], %1;" :: "r"(ad + 1024), "r"(pack_bf16(o[4 * j + 2] * l1, o[4 * j + 3] * l1)) : "memory");
            }
            fence_async();
            CK_(11); if (ft == 0) GT_(93);
            bar_sync(4, 256);
            CK_(12);
            reg_fence(gy); reg_fence(gz);
            wg_fence();
#pragma unroll
            for (int k = 0; k < 8; k++) wgmma_rs_n32(ay, gy[k][0], gy[k][1], gy[k][2], gy[k][3], dob + 512 + (k >> 2) * 256 + (k & 3) * 2, 1);
#pragma unroll
            for (int k = 0; k < 8; k++) wgmma_rs_n32(az, gz[k][0], gz[k][1], gz[k][2], gz[k][3], dob + 512 + (k >> 2) * 256 + (k & 3) * 2, 1);
            wg_commit();
            mbar_wait(bars + 8 * (WF + 2), 0);
            mbar_wait(bars + 8 * (WF + 3), 0);
            mbar_wait(bars + 8 * PA, 0);
            CK_(8);
            wg_fence();
#pragma unroll
            for (int k = 0; k < 8; k++) wgmma_ss_n32_ta(ay, dw2 + (k >> 2) * 1024 + (k & 3) * 128, dpo + (k >> 2) * 256 + (k & 3) * 2, 1);
#pragma unroll
            for (int k = 0 == 2 ? 4 : 0; k < 8; k++) wgmma_ss_n32_ta(az, dw3 + (k >> 2) * 1024 + (k & 3) * 128, dpo + (k >> 2) * 256 + (k & 3) * 2, 1);
            wg_commit();
            part = g_part + (size_t)(fc_ * 16 + ((ft >> 5) & 3)) * PW + (ft & 2) * 8 + ((ft >> 1) & 14) + (ft & 1);
            pcnt = g_pcnt + ((fc_ >> 4) * 28 + (fc_ & 1) * 16 + ((ft >> 5) & 3)) * 32;
            ep = lds32(sb + OFF_EP);
            asm volatile("" : "+l"(part), "+l"(pcnt), "+r"(ep));
            PBWAIT();
            CK_(13); if (ft == 0) GT_(94);
            wg_fence();
#pragma unroll
            for (int k = 0; k < 8; k++) wgmma_ss_n32_ta(ay, dw2 + 512 + (k >> 2) * 1024 + (k & 3) * 128, dpo + 512 + (k >> 2) * 256 + (k & 3) * 2, 1);
            wg_commit();
#pragma unroll
            for (int k = 0; k < 8; k++) wgmma_ss_n32_ta(az, dw3 + 512 + (k >> 2) * 1024 + (k & 3) * 128, dpo + 512 + (k >> 2) * 256 + (k & 3) * 2, 1);
            wg_commit();
        }
        wg_wait<1>(); reg_fence(ay); reg_fence(gy); reg_fence(gz);
        CK_(14); st_part(part + 4 * PW, pcnt + 128, ay, ep, lane); CK_(15);
        wg_wait<0>(); reg_fence(az);
        CK_(16); st_part(part + 8 * PW, pcnt + 256, az, ep, lane); CK_(17);
        if (tid == 0) STAMP(6);
    } else {
        if (tid == 128) {
            mbar_arrive(bars + 8 * SFREE);
            mbar_arrive_remote(mapa(bars + 8 * SFREE, rank ^ 1));
            mbar_wait(bars + 8 * SFREE, 0);
            long long tn = clock64();
#pragma unroll 1
            for (int i = 0; i < SC.n1; i++) {
                if (i >= 1) {
                    tn += 1300;
                    while (!mbar_test(bars + 8 * QRDY, 0) && clock64() < tn) {}
                }
                produce(mp, i, i + 1, sb, rank, row8);
            }
            if (0) {
                if (1) mbar_wait(bars + 8 * QRDY, 0);
                const size_t r3 = (size_t)(row8 + ((grp * 5 + 3) & 31) * 8) * 4096 + rank * 16384;
                const size_t r4 = (size_t)(row8 + ((grp * 5 + 4) & 31) * 8) * 4096 + rank * 16384;
                if (0 & 1) asm volatile("cp.async.bulk.prefetch.L2.global.L2::cache_hint [%0], %1, %2;" :: "l"(mp.kp + r3), "r"(16384), "l"(EVF) : "memory");
                if (0 & 2) asm volatile("cp.async.bulk.prefetch.L2.global.L2::cache_hint [%0], %1, %2;" :: "l"(mp.vp + r3), "r"(16384), "l"(EVF) : "memory");
                if (0 & 4) asm volatile("cp.async.bulk.prefetch.L2.global.L2::cache_hint [%0], %1, %2;" :: "l"(mp.kp + r4), "r"(16384), "l"(EVF) : "memory");
                if (0 & 8) asm volatile("cp.async.bulk.prefetch.L2.global.L2::cache_hint [%0], %1, %2;" :: "l"(mp.vp + r4), "r"(16384), "l"(EVF) : "memory");
            }
            produce(mp, SC.n1, SC.n2, sb, rank, row8);
        }
        __syncwarp();
        uint32_t fa[16][4], fb[16][4], fc[16][4];
        {
            const int r = lane & 7, h = lane >> 4, j = (lane >> 3) & 1;
            const uint32_t ad = sb + OFF_W + (h * 8 + r) * 128 + (((2 * warp + j) ^ r) << 4);
            mbar_wait(bars + 8 * (WF + 4), 0);
#pragma unroll
            for (int k = 0; k < 16; k++) ldsm_t4(fa[k], ad + k * 2048);
            mbar_wait(bars + 8 * (WF + 5), 0);
#pragma unroll
            for (int k = 0; k < 16; k++) ldsm_t4(fb[k], ad + 2 * U + k * 2048);
            reg_fence(fa); reg_fence(fb);
            bar_sync(3, 128);
            if (tid == 128) produce(mp, SC.n2, SC.n3, sb, rank, row8);
            __syncwarp();
            mbar_wait(bars + 8 * (WF + 6), 0);
#pragma unroll
            for (int k = 0; k < 16; k++) ldsm_t4(fc[k], ad + k * 2048);
            reg_fence(fc);
            bar_sync(3, 128);
        }
        if (1 == 1 || tid >= 160) {
            if (1 == 2) mbar_wait(bars + 8 * (KF + 2), 0), mbar_wait(bars + 8 * (WF + 2), 0);
            const uint32_t iv = (lds32(sb + OFF_EP) & 1) ^ 1;
            uint4* pw = (uint4*)(g_part + (size_t)fresh_cta() * 16 * PW);
            for (int i = 1 == 1 ? tid - 128 : tid - 160; i < 1024; i += 1 == 1 ? 128 : 96)
                if ((6 >> (i >> 8)) & 1) st_relaxed(pw + i, iv, iv, iv, iv);
        }
        if (tid == 128) {
            produce(mp, SC.n3, SC.n, sb, rank, row8);
            STAMP(9);
        }
        __syncwarp();
        const uint32_t obuf = sb + OUN * U;
        const uint64_t dob = make_desc(obuf, 16, 1024), dpo = make_desc(sb + OFF_PO, 16, 1024);
        bar_sync(2, 256);
        CK1_(32);
        if (fresh_tid() == 128) {
            mbar_wait(bars + 8 * (KE + 31 % RK), (31 / RK) & 1);
            const uint32_t rsb = mapa(sb, (fresh_cta() & 1) ^ 1); dsmem_copy(rsb + OFF_PO, obuf, 8192, rsb + OFF_BAR + 8 * PA);
        }
        __syncwarp();
        float ax[16], a3[16];
        reg_fence(fa); reg_fence(fb); reg_fence(fc);
        wg_fence();
#define OPROJ(acc, f, c1, db, first) \
        _Pragma("unroll") for (int k = 0; k < 8; k++) { const int kk = (k >> 2) * 8 + (c1) * 4 + (k & 3); \
            wgmma_rs_n32(acc, f[kk][0], f[kk][1], f[kk][2], f[kk][3], db + (c1) * 512 + (k >> 2) * 256 + (k & 3) * 2, (first) ? k : 1); }
        OPROJ(ax, fa, 0, dob, 1)
        OPROJ(a3, fc, 0, dob, 1)
        wg_commit();
        CK1_(33);
        mbar_wait(bars + 8 * PA, 0);
        CK1_(34);
        wg_fence();
        OPROJ(ax, fb, 0, dpo, 0)
        wg_commit();
        bar_sync(4, 256);
        CK1_(35);
        if (fresh_tid() == 128) { const uint32_t rsb = mapa(sb, (fresh_cta() & 1) ^ 1); dsmem_copy(rsb + OFF_PO + 8192, obuf + 8192, 8192, rsb + OFF_BAR + 8 * PB); }
        __syncwarp();
        wg_fence();
        OPROJ(a3, fc, 1, dob, 0)
        wg_commit();
        OPROJ(ax, fa, 1, dob, 0)
        wg_commit();
        wg_wait<1>(); reg_fence(a3); reg_fence(fc);
        const int ft = fresh_tid(), fc_ = fresh_cta(), lane = ft & 31;
        uint64_t* part = g_part + (size_t)(fc_ * 16 + ((ft >> 5) & 3)) * PW + (ft & 2) * 8 + ((ft >> 1) & 14) + (ft & 1);
        unsigned int* pcnt = g_pcnt + ((fc_ >> 4) * 28 + ((ft >> 5) & 3)) * 32;
        const uint32_t ep = lds32(sb + OFF_EP);
        CK1_(36); st_part(part + 12 * PW, pcnt + 384, a3, ep, lane); CK1_(37);
        PBWAIT();
        CK1_(38);
        wg_fence();
        OPROJ(ax, fb, 1, dpo, 0)
        wg_commit();
        wg_wait<0>(); reg_fence(ax); reg_fence(fa); reg_fence(fb); CK1_(39); st_part(part, pcnt + (fc_ & 1) * 512, ax, ep, lane); CK1_(40);

    }

    {
        const int ft = fresh_tid(), fc_ = fresh_cta();
        const int lane = ft & 31, w = ft >> 5, b = fc_ >> 4, rr = (fc_ & 1) ^ 1;
        const uint32_t ep = lds32(sb + OFF_EP);
        const bool full = w < 6;
        const int R = full ? ((fc_ >> 1) & 7) * 6 + w : (fc_ & 15) * 2 + w - 6;
        const int grpw = full ? R >> 2 : 12 + (R >> 3), cr = full ? rr : lane >> 4;
        const int uj = full ? R & 3 : (R >> 1) & 3, ul = full ? lane : (R & 1) * 16 + (lane & 15);
        const int blk4 = full ? rr * 16 + grpw : grpw;
        if (w >= 0 || !((6 >> (grpw >> 2)) & 1))
        cnt_wait(g_pcnt + (b * 28 + blk4) * 32, ep * (full ? 8 : 16) - (((6 >> (grpw >> 2)) & 1) ? 3 : 0), lane);
        float s0, s1, s2, s3;
        for (uint32_t n = 0;; n++) {
            s0 = 0.f; s1 = 0.f; s2 = 0.f; s3 = 0.f;
            uint32_t bad = 0;
            const uint64_t* src = g_part + (size_t)((b * 16 + cr) * 16 + grpw) * PW + uj * 32 + ul;
            uint64_t v[8];
#pragma unroll
            for (int i = 0; i < 8; i++) asm volatile("ld.relaxed.gpu.global.b64 %0, [%1];" : "=l"(v[i]) : "l"(src + i * (32 * PW)) : "memory");
#pragma unroll
            for (int i = 0; i < 8; i++) {
                const uint32_t lo = (uint32_t)v[i], hi = (uint32_t)(v[i] >> 32);
                bad |= lo ^ ep;
                s0 += __uint_as_float(lo << 16); s1 += __uint_as_float(lo & 0xffff0000u);
                s2 += __uint_as_float(hi << 16); s3 += __uint_as_float(hi & 0xffff0000u);
            }
            if (__all_sync(0xffffffffu, !(bad & 1))) {
                break;
            }
            if (n > (1u << 20)) TIMEOUT(42)
            if (0) __nanosleep(0);
        }
        CK_(18 + (ft >> 7) * 23);
        if (!full) {
            const float u0 = __shfl_xor_sync(0xffffffffu, s0, 16), u1 = __shfl_xor_sync(0xffffffffu, s1, 16);
            const float u2 = __shfl_xor_sync(0xffffffffu, s2, 16), u3 = __shfl_xor_sync(0xffffffffu, s3, 16);
            s0 += u0; s1 += u1; s2 += u2; s3 += u3;
        }
        const uint32_t r0 = pack_bf16(s0, s2), r1 = pack_bf16(s1, s3);
        const bool o1 = ul & 2, o2 = ul & 4;
        const uint32_t x = __shfl_xor_sync(0xffffffffu, o1 ? r0 : r1, 2), lo = o1 ? x : r0, hi = o1 ? r1 : x;
        const uint32_t p0 = __byte_perm(lo, hi, 0x5410), p1 = __byte_perm(lo, hi, 0x7632);
        const uint32_t y = __shfl_xor_sync(0xffffffffu, o2 ? p0 : p1, 4);
        const int q = uj * 8 + (ul >> 4) * 4 + (ul & 1) * 2 + (o1 ? 1 : 0), n0 = blk4 * 16 + (o2 ? 8 : 0) + ((ul >> 1) & 4);
        if (full || lane < 16) *(uint2*)(out + (size_t)(b * SQ + q) * DM + n0) = o2 ? make_uint2(y, p1) : make_uint2(p0, y);
    }
    if (fresh_tid() == 0) STAMP(8);
}

typedef CUresult (*EncodeFn)(CUtensorMap*, CUtensorMapDataType, cuuint32_t, void*, const cuuint64_t*, const cuuint64_t*,
                             const cuuint32_t*, const cuuint32_t*, CUtensorMapInterleave, CUtensorMapSwizzle,
                             CUtensorMapL2promotion, CUtensorMapFloatOOBfill);

void make_map(CUtensorMap* m, EncodeFn enc, const void* ptr, int nd, const cuuint64_t* dims, const cuuint64_t* strides, const cuuint32_t* box,
              CUtensorMapL2promotion promo = CU_TENSOR_MAP_L2_PROMOTION_L2_256B) {
    cuuint32_t es[4] = {1, 1, 1, 1};
    enc(m, CU_TENSOR_MAP_DATA_TYPE_BFLOAT16, nd, const_cast<void*>(ptr), dims, strides, box, es, CU_TENSOR_MAP_INTERLEAVE_NONE,
        CU_TENSOR_MAP_SWIZZLE_128B, promo, CU_TENSOR_MAP_FLOAT_OOB_FILL_NONE);
}

}

extern "C" void kernel_launch(void* const* d_in, const int* in_sizes, int n_in, void* d_out, int out_size) {
    static EncodeFn enc = nullptr;
    if (!enc) {
        cudaDriverEntryPointQueryResult qr;
        cudaGetDriverEntryPoint("cuTensorMapEncodeTiled", (void**)&enc, cudaEnableDefault, &qr);
        cudaFuncSetAttribute(fused_kernel, cudaFuncAttributeMaxDynamicSharedMemorySize, SMEM_BYTES);
    }
    Maps mp;
    cuuint64_t kd[4] = {64, 8, 4, (cuuint64_t)64 * SK / 8}, ks[3] = {512, 128, 4096};
    cuuint32_t kb[4] = {64, 8, 4, 4};
    make_map(&mp.k, enc, d_in[1], 4, kd, ks, kb);
    cuuint64_t vd[4] = {64, (cuuint64_t)64 * SK, 2, 2}, vs[3] = {512, 256, 128};
    cuuint32_t vb[4] = {64, 64, 2, 1}, vhb[4] = {64, 64, 1, 1};
    make_map(&mp.v, enc, d_in[2], 4, vd, vs, vb, CU_TENSOR_MAP_L2_PROMOTION_L2_128B);
    make_map(&mp.vh, enc, d_in[2], 4, vd, vs, vhb, CU_TENSOR_MAP_L2_PROMOTION_L2_128B);
    cuuint64_t xd[2] = {DM, 256}, xs[1] = {DM * 2}; cuuint32_t xb[2] = {64, 64};
    make_map(&mp.x, enc, d_in[0], 2, xd, xs, xb);
    cuuint64_t qd[2] = {4096, DM}, qs[1] = {8192}; cuuint32_t qb[2] = {64, 64};
    make_map(&mp.wq, enc, d_in[3], 2, qd, qs, qb);
    cuuint64_t od[4] = {DM, 64, 2, 32}, os[3] = {DM * 2, 64 * DM * 2, 128 * DM * 2}; cuuint32_t ob[4] = {64, 64, 1, 4};
    make_map(&mp.wo, enc, d_in[4], 4, od, os, ob);
    mp.wop = (const unsigned char*)d_in[4]; mp.wqp = (const unsigned char*)d_in[3]; mp.kp = (const unsigned char*)d_in[1]; mp.vp = (const unsigned char*)d_in[2]; mp.outp = (const unsigned char*)d_out;
    fused_kernel<<<128, 256, SMEM_BYTES>>>(mp, (__nv_bfloat16*)d_out);
}
```
